```python
import torch

def _softmax(x, axis=-1):
    return torch.softmax(x, dim=axis)
def _gelu(x):
    return torch.nn.functional.gelu(x, approximate="tanh")
def _silu(x):
    return torch.nn.functional.silu(x)
def _sigmoid(x):
    return torch.sigmoid(x)
def _layernorm(x, axis=-1, eps=1e-5):
    m = x.mean(dim=axis, keepdim=True)
    v = x.var(dim=axis, keepdim=True, unbiased=False)
    return (x - m) / torch.sqrt(v + eps)
def _scatter_add(tgt, idx, src, axis=0):
    return tgt.clone().index_add_(axis, idx, src)
def _segment_sum(src, seg, n):
    out = torch.zeros((n,) + src.shape[1:], dtype=src.dtype)
    return out.index_add_(0, seg, src)
def _pad(x, pw):
    flat = tuple(v for pair in reversed(pw) for v in pair)
    return torch.nn.functional.pad(x, flat)

kernel_name = 'standalone__dense_activation_squared_relu__prompt'

def setup_inputs():

    _w = (lambda a: (lambda t: t.to(torch.bfloat16) if t.is_floating_point() else t)(torch.as_tensor(a)))
    B, S, D, F = 1, 2048, 640, 1536
    return {
        "x": _w((lambda *s: torch.randn(*s, dtype=torch.bfloat16) * 0.05)(B, S, D)),
        "w1": _w((lambda *s: torch.randn(*s, dtype=torch.bfloat16) * 0.05)(D, F)),
        "b1": _w((lambda *s: torch.randn(*s, dtype=torch.bfloat16) * 0.05)(F)),
        "w2": _w((lambda *s: torch.randn(*s, dtype=torch.bfloat16) * 0.05)(F, D)),
        "b2": _w((lambda *s: torch.randn(*s, dtype=torch.bfloat16) * 0.05)(D)),
    }

def reference(x, w1, b1, w2, b2):
    h = torch.einsum("bsd,df->bsf", x, w1) + b1
    zero = torch.zeros_like(h)
    r = torch.where(h > zero, h, zero)
    h = r * r
    out = torch.einsum("bsf,fd->bsd", h, w2) + b2
    return out
```

```cpp
#include <cuda_runtime.h>
#include <cuda_bf16.h>
#include <cuda.h>
#include <stdint.h>

namespace {

constexpr int S_TOK = 2048, D_MODEL = 640, D_FF = 1536;
constexpr int TOK = 80;
constexpr int NTILE = 26;
constexpr int NCTA = NTILE * 5;
constexpr int NTHREADS = 512;

constexpr uint32_t ASLOT = 16384, NA = 7;
constexpr uint32_t BSLOT = TOK * 128, NB = 11;
constexpr uint32_t OFF_A = 0;
constexpr uint32_t OFF_B = NA * ASLOT;
constexpr uint32_t OFF_BAR = OFF_B + NB * BSLOT;
constexpr uint32_t OFF_EPOCH = OFF_BAR + 1536;
constexpr uint32_t SMEM_BYTES = OFF_BAR + 4096;

constexpr uint32_t B_FULL1 = 0;
constexpr uint32_t B_EPOCH = 30;
constexpr uint32_t B_FIRST = 31;
constexpr uint32_t B_RAW = 32;
constexpr uint32_t B_FULL2 = 56;
constexpr uint32_t B_DONE2 = 80;
constexpr uint32_t B_DONE1 = 104;
constexpr uint32_t B_LEAD = 129;

constexpr uint32_t DESC_HI_SW128 = 0x40000040u;
constexpr uint32_t DESC_HI_H = 128 >> 4;
constexpr uint32_t H_LBO = 1280;
constexpr uint32_t SPIN_LIMIT = 1u << 21;

constexpr int HLOOK = 8;
constexpr int PF_W2 = 10, PF_N = 1;
constexpr int END_LEAD = 2;
constexpr uint32_t STORE_TICKS = 0x130f0c08;

__device__ __align__(1024) uint8_t g_h[NTILE * 24 * BSLOT];
__device__ uint32_t g_epoch[NCTA];

__device__ __forceinline__ void mbar_init(uint32_t bar, uint32_t cnt) {
    asm volatile("mbarrier.init.shared::cta.b64 [%0], %1;" ::"r"(bar), "r"(cnt) : "memory");
}
__device__ __forceinline__ void mbar_expect_tx(uint32_t bar, uint32_t bytes) {
    asm volatile("mbarrier.arrive.expect_tx.shared::cta.b64 _, [%0], %1;" ::"r"(bar), "r"(bytes) : "memory");
}
__device__ __forceinline__ void mbar_arrive(uint32_t bar) {
    asm volatile("mbarrier.arrive.shared::cta.b64 _, [%0];" ::"r"(bar) : "memory");
}
__device__ __forceinline__ void mbar_arrive_if(uint32_t bar, uint32_t pred) {
    asm volatile("{\n.reg .pred p;\nsetp.ne.u32 p, %1, 0;\n@p mbarrier.arrive.shared::cta.b64 _, [%0];\n}"
                 ::"r"(bar), "r"(pred) : "memory");
}
__device__ __forceinline__ void mbar_spin(uint32_t bar, uint32_t parity = 0) {
    asm volatile("{\n.reg .pred p;\nWAIT:\nmbarrier.try_wait.parity.shared::cta.b64 p, [%0], %1;\n@!p bra WAIT;\n}"
                 ::"r"(bar), "r"(parity) : "memory");
}
__device__ __forceinline__ void watchdog(uint32_t bar) {
    uint32_t n = 0, ok;
    do {
        asm volatile("{\n.reg .pred p;\nmbarrier.try_wait.parity.shared::cta.b64 p, [%1], 0, 1000;\nselp.u32 %0, 1, 0, p;\n}"
                     : "=r"(ok) : "r"(bar) : "memory");
        if (++n > SPIN_LIMIT) __trap();
    } while (!ok);
}
__device__ __forceinline__ bool elect_one() {
    uint32_t p;
    asm volatile("{\n.reg .pred P;\nelect.sync _|P, 0xffffffff;\nselp.u32 %0, 1, 0, P;\n}" : "=r"(p));
    return p;
}
__device__ __forceinline__ void tma_2d(uint32_t dst, const CUtensorMap* m, int c0, int c1, uint32_t bar) {
    asm volatile("cp.async.bulk.tensor.2d.shared::cluster.global.mbarrier::complete_tx::bytes [%0], [%1, {%3, %4}], [%2];"
                 ::"r"(dst), "l"(m), "r"(bar), "r"(c0), "r"(c1) : "memory");
}
__device__ __forceinline__ void tma_3d(uint32_t dst, const CUtensorMap* m, int c0, int c1, int c2, uint32_t bar) {
    asm volatile("cp.async.bulk.tensor.3d.shared::cluster.global.mbarrier::complete_tx::bytes [%0], [%1, {%3, %4, %5}], [%2];"
                 ::"r"(dst), "l"(m), "r"(bar), "r"(c0), "r"(c1), "r"(c2) : "memory");
}
__device__ __forceinline__ void tma_store_2d(const CUtensorMap* m, uint32_t src, int c0, int c1) {
    asm volatile("cp.async.bulk.tensor.2d.global.shared::cta.bulk_group [%0, {%2, %3}], [%1];"
                 ::"l"(m), "r"(src), "r"(c0), "r"(c1) : "memory");
}
__device__ __forceinline__ void bulk_load(uint32_t dst, const void* src, uint32_t bytes, uint32_t bar) {
    asm volatile("cp.async.bulk.shared::cluster.global.mbarrier::complete_tx::bytes [%0], [%1], %2, [%3];"
                 ::"r"(dst), "l"(src), "r"(bytes), "r"(bar) : "memory");
}
__device__ __forceinline__ void bulk_prefetch(const void* src, uint32_t bytes) {
    asm volatile("cp.async.bulk.prefetch.L2.global [%0], %1;" ::"l"(src), "r"(bytes) : "memory");
}
__device__ __forceinline__ void prefetch_l2(const void* p) {
    asm volatile("prefetch.global.L2 [%0];" ::"l"(p) : "memory");
}
__device__ __forceinline__ void prefetch_map(const CUtensorMap* m) {
    asm volatile("prefetch.tensormap [%0];" ::"l"(m) : "memory");
}
__device__ __forceinline__ uint32_t ldg_u16(const uint16_t* p) {
    uint32_t v;
    asm volatile("ld.global.nc.u16 %0, [%1];" : "=r"(v) : "l"(p));
    return v;
}
__device__ __forceinline__ uint32_t late(uint32_t v) {
    asm volatile("" : "+r"(v)::"memory");
    return v;
}
__device__ __forceinline__ void wg_fence() { asm volatile("wgmma.fence.sync.aligned;" ::: "memory"); }
__device__ __forceinline__ void wg_commit() { asm volatile("wgmma.commit_group.sync.aligned;" ::: "memory"); }
template <int N> __device__ __forceinline__ void wg_wait() {
    asm volatile("wgmma.wait_group.sync.aligned %0;" ::"n"(N) : "memory");
}
__device__ __forceinline__ void reg_fence(float (&d)[40]) {
#pragma unroll
    for (int i = 0; i < 40; i++) asm volatile("" : "+f"(d[i])::"memory");
}
__device__ __forceinline__ void stsm_x4_t(uint32_t addr, uint32_t a, uint32_t b, uint32_t c, uint32_t d) {
    asm volatile("stmatrix.sync.aligned.m8n8.x4.trans.shared.b16 [%0], {%1, %2, %3, %4};"
                 ::"r"(addr), "r"(a), "r"(b), "r"(c), "r"(d) : "memory");
}
__device__ __forceinline__ uint32_t pack_bf16(float lo, float hi) {
    uint32_t r;
    asm("cvt.rn.bf16x2.f32 %0, %1, %2;" : "=r"(r) : "f"(hi), "f"(lo));
    return r;
}
__device__ __forceinline__ uint32_t add_bf16(uint32_t a, uint32_t b) {
    uint32_t r;
    asm("add.rn.bf16x2 %0, %1, %2;" : "=r"(r) : "r"(a), "r"(b));
    return r;
}
__device__ __forceinline__ uint32_t act(float lo, float hi, uint32_t bias) {
    uint32_t h = add_bf16(pack_bf16(lo, hi), bias), r;
    asm("max.bf16x2 %0, %1, %2;" : "=r"(r) : "r"(h), "r"(0u));
    asm("mul.rn.bf16x2 %0, %1, %1;" : "=r"(h) : "r"(r));
    return h;
}

__device__ __forceinline__ void mma_x(float (&d)[40], uint32_t alo, uint32_t blo, uint32_t acc) {
    asm volatile(
        "{\n.reg .pred p;\n.reg .b64 da, db;\n"
        "setp.ne.b32 p, %42, 0;\n"
        "mov.b64 da, {%40, %43};\nmov.b64 db, {%41, %44};\n"
        "wgmma.mma_async.sync.aligned.m64n80k16.f32.bf16.bf16 "
        "{%0, %1, %2, %3, %4, %5, %6, %7, %8, %9, %10, %11, %12, %13, %14, %15, "
        "%16, %17, %18, %19, %20, %21, %22, %23, %24, %25, %26, %27, %28, %29, %30, %31, "
        "%32, %33, %34, %35, %36, %37, %38, %39}, "
        "da, db, p, 1, 1, 1, 0;\n}\n"
        : "+f"(d[0]), "+f"(d[1]), "+f"(d[2]), "+f"(d[3]), "+f"(d[4]), "+f"(d[5]), "+f"(d[6]), "+f"(d[7]),
          "+f"(d[8]), "+f"(d[9]), "+f"(d[10]), "+f"(d[11]), "+f"(d[12]), "+f"(d[13]), "+f"(d[14]), "+f"(d[15]),
          "+f"(d[16]), "+f"(d[17]), "+f"(d[18]), "+f"(d[19]), "+f"(d[20]), "+f"(d[21]), "+f"(d[22]), "+f"(d[23]),
          "+f"(d[24]), "+f"(d[25]), "+f"(d[26]), "+f"(d[27]), "+f"(d[28]), "+f"(d[29]), "+f"(d[30]), "+f"(d[31]),
          "+f"(d[32]), "+f"(d[33]), "+f"(d[34]), "+f"(d[35]), "+f"(d[36]), "+f"(d[37]), "+f"(d[38]), "+f"(d[39])
        : "r"(alo), "r"(blo), "r"(acc), "n"(DESC_HI_SW128), "n"(DESC_HI_SW128));
}

__device__ __forceinline__ void mma_h(float (&d)[40], uint32_t alo, uint32_t blo, uint32_t acc) {
    asm volatile(
        "{\n.reg .pred p;\n.reg .b64 da, db;\n"
        "setp.ne.b32 p, %42, 0;\n"
        "mov.b64 da, {%40, %43};\nmov.b64 db, {%41, %44};\n"
        "wgmma.mma_async.sync.aligned.m64n80k16.f32.bf16.bf16 "
        "{%0, %1, %2, %3, %4, %5, %6, %7, %8, %9, %10, %11, %12, %13, %14, %15, "
        "%16, %17, %18, %19, %20, %21, %22, %23, %24, %25, %26, %27, %28, %29, %30, %31, "
        "%32, %33, %34, %35, %36, %37, %38, %39}, "
        "da, db, p, 1, 1, 1, 1;\n}\n"
        : "+f"(d[0]), "+f"(d[1]), "+f"(d[2]), "+f"(d[3]), "+f"(d[4]), "+f"(d[5]), "+f"(d[6]), "+f"(d[7]),
          "+f"(d[8]), "+f"(d[9]), "+f"(d[10]), "+f"(d[11]), "+f"(d[12]), "+f"(d[13]), "+f"(d[14]), "+f"(d[15]),
          "+f"(d[16]), "+f"(d[17]), "+f"(d[18]), "+f"(d[19]), "+f"(d[20]), "+f"(d[21]), "+f"(d[22]), "+f"(d[23]),
          "+f"(d[24]), "+f"(d[25]), "+f"(d[26]), "+f"(d[27]), "+f"(d[28]), "+f"(d[29]), "+f"(d[30]), "+f"(d[31]),
          "+f"(d[32]), "+f"(d[33]), "+f"(d[34]), "+f"(d[35]), "+f"(d[36]), "+f"(d[37]), "+f"(d[38]), "+f"(d[39])
        : "r"(alo), "r"(blo), "r"(acc), "n"(DESC_HI_SW128), "n"(DESC_HI_H));
}

__device__ __forceinline__ void mma_hn(float (&d)[40], uint32_t alo, uint32_t blo, uint32_t acc) {
    asm volatile(
        "{\n.reg .pred p;\n.reg .b64 da, db;\n"
        "setp.ne.b32 p, %42, 0;\n"
        "mov.b64 da, {%40, %43};\nmov.b64 db, {%41, %44};\n"
        "wgmma.mma_async.sync.aligned.m64n80k16.f32.bf16.bf16 "
        "{%0, %1, %2, %3, %4, %5, %6, %7, %8, %9, %10, %11, %12, %13, %14, %15, "
        "%16, %17, %18, %19, %20, %21, %22, %23, %24, %25, %26, %27, %28, %29, %30, %31, "
        "%32, %33, %34, %35, %36, %37, %38, %39}, "
        "da, db, p, 1, -1, 1, 1;\n}\n"
        : "+f"(d[0]), "+f"(d[1]), "+f"(d[2]), "+f"(d[3]), "+f"(d[4]), "+f"(d[5]), "+f"(d[6]), "+f"(d[7]),
          "+f"(d[8]), "+f"(d[9]), "+f"(d[10]), "+f"(d[11]), "+f"(d[12]), "+f"(d[13]), "+f"(d[14]), "+f"(d[15]),
          "+f"(d[16]), "+f"(d[17]), "+f"(d[18]), "+f"(d[19]), "+f"(d[20]), "+f"(d[21]), "+f"(d[22]), "+f"(d[23]),
          "+f"(d[24]), "+f"(d[25]), "+f"(d[26]), "+f"(d[27]), "+f"(d[28]), "+f"(d[29]), "+f"(d[30]), "+f"(d[31]),
          "+f"(d[32]), "+f"(d[33]), "+f"(d[34]), "+f"(d[35]), "+f"(d[36]), "+f"(d[37]), "+f"(d[38]), "+f"(d[39])
        : "r"(alo), "r"(blo), "r"(acc), "n"(DESC_HI_SW128), "n"(DESC_HI_H));
}


__global__ void __launch_bounds__(NTHREADS, 1)
mlp_kernel(const __grid_constant__ CUtensorMap map_x, const __grid_constant__ CUtensorMap map_w1,
           const __grid_constant__ CUtensorMap map_w2, const __grid_constant__ CUtensorMap map_out,
           const uint8_t* __restrict__ x, const uint8_t* __restrict__ w1, const uint8_t* __restrict__ w2,
           const uint16_t* __restrict__ b1, const uint16_t* __restrict__ b2, uint8_t* hbuf, uint32_t* epoch)
{
    extern __shared__ __align__(1024) uint8_t smem_raw[];
    uint32_t sbase = (uint32_t)__cvta_generic_to_shared(smem_raw);
    asm volatile("" : "+r"(sbase));
    const int lane = threadIdx.x & 31;
    const int b = blockIdx.x;
    const int tt = b / 5, dt = b - tt * 5;
    auto bar = [&](uint32_t i) { return sbase + OFF_BAR + 8 * i; };
    auto load_x = [&](uint32_t s) {
        tma_2d(sbase + OFF_B + s * BSLOT, &map_x, s * 64, tt * TOK, bar(B_FULL1 + s));
        tma_2d(sbase + OFF_B + (s + 1) * BSLOT, &map_x, s * 64 + 64, tt * TOK, bar(B_FULL1 + s));
    };
    auto load_w1 = [&](uint32_t dst, int chunk, int k0, uint32_t fb) {
        tma_2d(dst, &map_w1, (dt + 5 * chunk) * 64, k0, fb);
        tma_2d(dst + 8192, &map_w1, (dt + 5 * chunk) * 64, k0 + 64, fb);
    };

    if (threadIdx.x - 32u < 64u) {
        const uint32_t t = threadIdx.x - 32, n = (t - 32) * NCTA + b;
        if (t < 32) prefetch_l2(x + (size_t)min(tt * TOK + dt * 16 + (int)(t & 15), S_TOK - 1) * (D_MODEL * 2) + (t >> 4) * 128);
        else if (t < 42) prefetch_l2(w1 + (size_t)(n / 10) * (D_FF * 2) + (n % 10) * 128);
    }
    if (threadIdx.x < 32) {
        if (elect_one()) {
            mbar_init(bar(B_FIRST), 1);
#pragma unroll
            for (int s = 0; s < 7; s++) mbar_init(bar(B_FULL1 + s), 1);
            mbar_expect_tx(bar(B_FIRST), BSLOT + 8192);
            tma_2d(sbase + OFF_B, &map_x, 0, tt * TOK, bar(B_FIRST));
            tma_2d(sbase + OFF_A, &map_w1, dt * 64, 0, bar(B_FIRST));
        }
        __syncwarp();
        asm volatile("bar.arrive 3, 288;" ::: "memory");
        if (elect_one()) {
            mbar_expect_tx(bar(B_FULL1), BSLOT + 8192);
            tma_2d(sbase + OFF_B + BSLOT, &map_x, 64, tt * TOK, bar(B_FULL1));
            tma_2d(sbase + OFF_A + 8192, &map_w1, dt * 64, 64, bar(B_FULL1));
#pragma unroll
            for (uint32_t s = 1; s < 7; s++) {
                mbar_expect_tx(bar(B_FULL1 + s), (s & 1) ? ASLOT : ASLOT + 2 * BSLOT);
                if ((s & 1) == 0) load_x(s);
                load_w1(sbase + OFF_A + s * ASLOT, s & 1, (s >> 1) * 128, bar(B_FULL1 + s));
            }
        }
        __syncwarp();
    }

    const int hw = __shfl_sync(0xffffffffu, threadIdx.x >> 5, 0);
    const int warp = hw < 4 ? hw + 8 : hw < 12 ? hw - 4 : hw;
    const int nchunk = dt < 4 ? 5 : 4;
    const int n1 = nchunk * 5;
    auto parity = [&]() {
        uint32_t v;
        mbar_spin(bar(B_EPOCH));
        asm volatile("ld.shared.u32 %0, [%1];" : "=r"(v) : "r"(sbase + OFF_EPOCH) : "memory");
        return v & 1;
    };

    uint32_t early[6];
    if (warp < 8) {
        asm volatile("bar.sync 3, 288;" ::: "memory");
    } else {
        if (warp == 13) early[0] = epoch[b];
        if (warp > 8 && elect_one()) {
            if (warp < 14) {
                const uint32_t first = warp == 9 ? 7 : warp == 10 ? B_RAW : warp == 11 ? B_FULL2 : warp == 12 ? B_DONE2 : B_DONE1;
                const uint32_t cnt = warp < 11 ? 1 : warp == 11 ? 2 : warp == 12 ? 8 : 4;
#pragma unroll
                for (uint32_t i = 0; i < 16; i++) mbar_init(bar(first + i), cnt);
            } else {
#pragma unroll
                for (uint32_t i = 16; i < 24; i++) {
                    mbar_init(bar((warp == 14 ? 7 : B_RAW) + i), 1);
                    mbar_init(bar((warp == 14 ? B_FULL2 : B_DONE2) + i), warp == 14 ? 2 : 8);
                }
#pragma unroll
                for (uint32_t i = 0; i < (26 - 16) / 2; i++) mbar_init(bar(B_DONE1 + 16 + 2 * i + warp - 14), 4);
            }
        }
        __syncwarp();
        if (warp == 8) asm volatile("bar.sync 5, 64;" ::: "memory");
        else asm volatile("bar.sync 4, %0;" ::"n"(NTHREADS - 32) : "memory");
        if (warp == 9) asm volatile("bar.arrive 5, 64;" ::: "memory");
    }

    if (warp < 12) {
        const int wg = warp >> 2;
        {
            const int r = (warp & 3) * 16 + (lane >> 2);
#pragma unroll
            for (int i = 0; i < 2; i++) {
                const int g = min(dt + 5 * (wg + 3 * i), 23);
                early[2 * i] = ldg_u16(b1 + g * 64 + r);
                early[2 * i + 1] = ldg_u16(b1 + g * 64 + r + 8);
            }
            early[4] = ldg_u16(b2 + dt * 128 + (wg >> 1) * 64 + r);
            early[5] = ldg_u16(b2 + dt * 128 + (wg >> 1) * 64 + r + 8);
        }
        const uint32_t lo = (sbase & 0x3FFFFu) >> 4;
        const uint32_t dA = lo + (OFF_A >> 4) + (1u << 16);
        const uint32_t dX = lo + (OFF_B >> 4) + (1u << 16);
        const uint32_t dH = lo + (OFF_B >> 4) + ((H_LBO >> 4) << 16);
        const uint32_t lead = lane == 0;
        float acc[40];
        auto half = [&](uint32_t a, uint32_t xb, bool first) {
#pragma unroll
            for (int kk = 0; kk < 4; kk++) mma_x(acc, a + kk * 128, xb + kk * 2, !(first && kk == 0));
        };
        auto store_h = [&](int c, uint32_t blo, uint32_t bhi) {
            reg_fence(acc);
            const uint32_t tag = parity() * 0x80008000u;
            uint32_t pk[20];
            blo = late(blo) * 0x10001u;
            bhi = late(bhi) * 0x10001u;
#pragma unroll
            for (int g = 0; g < 10; g++) {
                pk[2 * g] = act(acc[4 * g], acc[4 * g + 1], blo) | tag;
                pk[2 * g + 1] = act(acc[4 * g + 2], acc[4 * g + 3], bhi) | tag;
            }
            const uint32_t tick = c == 4 ? bar(B_DONE2) : bar(B_DONE1 + ((STORE_TICKS >> (8 * c)) & 255));
            uint8_t* dst = hbuf + (size_t)(tt * 24 + dt + 5 * c) * BSLOT + (warp & 3) * 2560 + lane * 4;
#pragma unroll
            for (int g = 0; g < 10; g++) {
                if (c == 4) mbar_spin(tick + 8 * g);
                else if (c != nchunk - 1 && (g == 0 || g == 4 || g == 7)) mbar_spin(tick + 8 * (g / 3));
                asm volatile("st.global.u32 [%0], %1;" ::"l"(dst + g * 128), "r"(pk[2 * g]) : "memory");
                asm volatile("st.global.u32 [%0], %1;" ::"l"(dst + 1280 + g * 128), "r"(pk[2 * g + 1]) : "memory");
            }
        };

        if (wg < 2) {
            const uint32_t fb = bar(B_FULL1 + wg), db = bar(B_DONE1 + wg);
            mbar_spin(bar(B_FIRST));
            if (wg) mbar_spin(fb);
            wg_fence();
            half(dA + wg * (ASLOT >> 4), dX, true);
            wg_commit();
            asm volatile("bar.sync 4, %0;" ::"n"(NTHREADS - 32) : "memory");
            mbar_spin(bar(B_FULL1));
            wg_fence();
            half(dA + wg * (ASLOT >> 4) + 512, dX + (BSLOT >> 4), false);
            wg_commit();
#pragma unroll
            for (int i = 1; i < 5; i++) {
                const uint32_t a = dA + (wg ? (2 * i + 1) % NA : (2 * i) % NA) * (ASLOT >> 4);
                mbar_spin(bar(B_FULL1 + 2 * i));
                mbar_spin(fb + 16 * i);
                wg_fence();
                half(a, dX + 2 * i * (BSLOT >> 4), false);
                half(a + 512, dX + (2 * i + 1) * (BSLOT >> 4), false);
                wg_commit();
                wg_wait<1>();
                mbar_arrive_if(db + 16 * (i - 1), lead);
            }
            wg_wait<0>();
            mbar_arrive_if(db + 64, lead);
            store_h(wg, early[0], early[1]);
        }
        const int c = wg == 2 ? 2 : wg + 3;
        if (c < nchunk) {
            const uint32_t fb = bar(B_FULL1 + 5 * c), db = bar(B_DONE1 + 5 * c);
            uint32_t slot = c == 2 ? 10 % NA : c == 3 ? 15 % NA : 20 % NA;
            if (c == 2) mbar_spin(bar(B_FULL1 + 8));
            mbar_spin(fb);
            mbar_spin(db - 16);
#pragma unroll
            for (int i = 0; i < 5; i++) {
                const uint32_t a = dA + slot * (ASLOT >> 4);
                slot = slot == NA - 1 ? 0 : slot + 1;
                wg_fence();
                half(a, dX + 2 * i * (BSLOT >> 4), i == 0);
                half(a + 512, dX + (2 * i + 1) * (BSLOT >> 4), false);
                wg_commit();
                if (i < 4) mbar_spin(fb + 8 * (i + 1));
                if (i > 0) {
                    wg_wait<1>();
                    mbar_arrive_if(db + 8 * (i - 1), lead);
                }
            }
            wg_wait<0>();
            mbar_arrive_if(db + 32, lead);
            store_h(c, wg == 2 ? early[0] : early[2], wg == 2 ? early[1] : early[3]);
        }
        if (wg == 1) return;

        const int dh = wg >> 1;
        uint32_t a2 = dA + (dt < 4 ? 25 % NA : 20 % NA) * (ASLOT >> 4) + dh * 512, h2 = dH + 10 * (BSLOT >> 4);
        const uint32_t a2_last = dA + (NA - 1) * (ASLOT >> 4) + dh * 512, h2_last = h2;
        uint32_t fb2 = bar(B_FULL2);
        const int hold_at = dh ? 24 - END_LEAD : -1;
#define STEP2(MMA, p)                                                                               \
        {                                                                                           \
            wg_fence();                                                                             \
            _Pragma("unroll") for (int kk = 0; kk < 4; kk++)                                        \
                MMA(acc, a2 + kk * 128, h2 + kk * (2 * H_LBO >> 4), ((p) | kk) != 0);               \
            wg_commit();                                                                            \
            a2 = a2 == a2_last ? a2 - (NA - 1) * (ASLOT >> 4) : a2 + (ASLOT >> 4);                  \
            h2 = h2 == h2_last ? dH : h2 + (BSLOT >> 4);                                            \
            fb2 += 8;                                                                               \
        }
#define PHASE2(MMA)                                                                                 \
        STEP2(MMA, 0);                                                                              \
        mbar_spin(fb2);                                                                             \
        _Pragma("unroll 1") for (int p = 1; p < 23; p++) {                                          \
            if (p == hold_at) mbar_spin(bar(B_LEAD));                                               \
            STEP2(MMA, p);                                                                          \
            mbar_spin(fb2);                                                                         \
            wg_wait<1>();                                                                           \
            mbar_arrive_if(fb2 + 8 * (B_DONE2 - B_FULL2 - 2), lead);                                \
        }                                                                                           \
        STEP2(MMA, 23);                                                                             \
        mbar_arrive_if(bar(B_LEAD), lead && !dh);                                                   \
        wg_wait<0>();
        const uint32_t odd = __shfl_sync(0xffffffffu, parity(), 0);
        mbar_spin(fb2);
        mbar_spin(bar(B_DONE1 + n1 - 2));
        if (odd) { PHASE2(mma_hn) } else { PHASE2(mma_h) }
#undef PHASE2
#undef STEP2
        const uint32_t b2lo = late(early[4]) * 0x10001u, b2hi = late(early[5]) * 0x10001u;
        reg_fence(acc);
        mbar_arrive_if(bar(B_DONE2 + 23), lead);

        const uint32_t otile = sbase + OFF_B + (2 + dh) * BSLOT;
        const uint32_t orow = otile + ((lane >> 4) * 8 + (lane & 7)) * 128 +
                              ((uint32_t)((((warp & 3) * 2 + ((lane >> 3) & 1)) ^ (lane & 7))) << 4);
#pragma unroll
        for (int g = 0; g < 10; g += 2) {
            const int i = g * 4;
            const uint32_t m0 = add_bf16(pack_bf16(acc[i + 0], acc[i + 1]), b2lo);
            const uint32_t m1 = add_bf16(pack_bf16(acc[i + 2], acc[i + 3]), b2hi);
            const uint32_t m2 = add_bf16(pack_bf16(acc[i + 4], acc[i + 5]), b2lo);
            const uint32_t m3 = add_bf16(pack_bf16(acc[i + 6], acc[i + 7]), b2hi);
            stsm_x4_t(orow + g * 1024, m0, m1, m2, m3);
        }
        asm volatile("fence.proxy.async.shared::cta;" ::: "memory");
        asm volatile("bar.sync %0, 128;" ::"r"(1 + dh) : "memory");
        if ((warp & 3) == 0 && elect_one()) {
            tma_store_2d(&map_out, otile, dt * 128 + dh * 64, tt * TOK);
            asm volatile("cp.async.bulk.commit_group;" ::: "memory");
            asm volatile("cp.async.bulk.wait_group.read 0;" ::: "memory");
        }
    } else if (warp == 12) {
        if (elect_one()) {
            prefetch_map(&map_w2);
            prefetch_map(&map_out);
            uint32_t dst = sbase + OFF_A, fb = bar(B_FULL1 + NA), db = bar(B_DONE1);
            auto next = [&]() {
                dst = dst == sbase + OFF_A + (NA - 1) * ASLOT ? sbase + OFF_A : dst + ASLOT;
                fb += 8;
                db += 8;
            };
            load_x(8);
#pragma unroll 1
            for (int s = NA; s < n1; s++) {
                const int chunk = s < 10 ? (s & 1) : s / 5, k0 = (s < 10 ? s >> 1 : s % 5) * 128;
                mbar_spin(db);
                load_w1(dst, chunk, k0, fb);
                next();
            }
            const uint8_t* hsrc = hbuf + (size_t)tt * 24 * BSLOT;
            auto load_h = [&](int p) {
                bulk_load(sbase + OFF_B + ((p + 10) % NB) * BSLOT, hsrc + p * BSLOT, BSLOT, bar(B_RAW + p));
            };
            fb = bar(B_FULL2);
#pragma unroll
            for (int q = 0; q < 25; q++) {
                if (q == NA) db = bar(B_DONE2);
                mbar_spin(db);
                if (q < 24) tma_3d(dst, &map_w2, 0, q * 64, 2 * dt, fb);
                next();
#pragma unroll
                for (int p = 0; p < 24; p++) {
                    const int due = p == 0 ? 1 : p < HLOOK ? 2 + max(p + 5 - HLOOK, (p - 1) >> 1) : p - HLOOK + 7;
                    if (p < 20) { if (due == q) load_h(p); }
                    else if (due == q) { if (dt < 4) load_h(p); }
                    else if (q == 24 && dt == 4) load_h(p);
                }
            }
        }
    } else if (warp == 13) {
        if (elect_one()) {
#pragma unroll 1
            for (int s = NA; s < 25; s++) mbar_expect_tx(bar(B_FULL1 + s), s == 8 ? ASLOT + 2 * BSLOT : ASLOT);
            const uint32_t now = early[0] + 1;
            asm volatile("st.shared.u32 [%0], %1;" ::"r"(sbase + OFF_EPOCH), "r"(now) : "memory");
            mbar_arrive(bar(B_EPOCH));
            epoch[b] = now;
#pragma unroll 1
            for (int p = 0; p < 24; p++) {
                mbar_expect_tx(bar(B_FULL2 + p), ASLOT);
                mbar_expect_tx(bar(B_RAW + p), BSLOT);
            }
            if (b < 128) {
#pragma unroll 1
                for (int i = 0; i < PF_N; i++) {
                    watchdog(bar(B_FULL1 + PF_W2 + i));
                    bulk_prefetch(w2 + (size_t)i * (D_FF * D_MODEL * 2 / PF_N) + b * (15360 / PF_N), 15360 / PF_N);
                }
            }
            watchdog(bar(B_DONE2 + 23));
        }
    } else {
        const uint32_t flip = parity() ? 0u : 0x80008000u;
        const uint32_t off = lane * 32 + ((lane >> 2) & 7) * 4;
#pragma unroll 1
        for (int p = warp - 14; p < 24; p += 2) {
            const uint32_t tile = sbase + OFF_B + ((p + 10) % NB) * BSLOT, raw = bar(B_RAW + p);
            for (uint32_t tries = 0;; tries++) {
                mbar_spin(raw, tries & 1);
                uint32_t ok = 0x80008000u;
#pragma unroll
                for (int i = 0; i < 10; i++) {
                    uint32_t v;
                    asm volatile("ld.shared.u32 %0, [%1];" : "=r"(v) : "r"(tile + off + i * 1024) : "memory");
                    ok &= v ^ flip;
                }
                if (__all_sync(0xffffffffu, ok == 0x80008000u)) break;
                if (elect_one()) {
                    mbar_expect_tx(raw, BSLOT);
                    bulk_load(tile, hbuf + (size_t)(tt * 24 + p) * BSLOT, BSLOT, raw);
                }
                __syncwarp();
            }
            mbar_arrive_if(bar(B_FULL2 + p), lane == 0);
        }
    }
}

__device__ __forceinline__ float rbf(float v) { return __bfloat162float(__float2bfloat16(v)); }
__global__ void fallback_h(const __nv_bfloat16* x, const __nv_bfloat16* w1, const __nv_bfloat16* b1, __nv_bfloat16* h) {
    const int f = blockIdx.x * blockDim.x + threadIdx.x, t = blockIdx.y;
    float a = 0.f;
    for (int k = 0; k < D_MODEL; k++) a += __bfloat162float(x[t * D_MODEL + k]) * __bfloat162float(w1[k * D_FF + f]);
    float v = rbf(rbf(a) + __bfloat162float(b1[f]));
    v = v > 0.f ? v : 0.f;
    h[t * D_FF + f] = __float2bfloat16(v * v);
}
__global__ void fallback_out(const __nv_bfloat16* h, const __nv_bfloat16* w2, const __nv_bfloat16* b2, __nv_bfloat16* out) {
    const int d = blockIdx.x * blockDim.x + threadIdx.x, t = blockIdx.y;
    float a = 0.f;
    for (int k = 0; k < D_FF; k++) a += __bfloat162float(h[t * D_FF + k]) * __bfloat162float(w2[k * D_MODEL + d]);
    out[t * D_MODEL + d] = __float2bfloat16(rbf(a) + __bfloat162float(b2[d]));
}

typedef CUresult (*EncodeFn)(CUtensorMap*, CUtensorMapDataType, cuuint32_t, void*, const cuuint64_t*, const cuuint64_t*,
                             const cuuint32_t*, const cuuint32_t*, CUtensorMapInterleave, CUtensorMapSwizzle,
                             CUtensorMapL2promotion, CUtensorMapFloatOOBfill);

void encode(EncodeFn fn, CUtensorMap* m, const void* ptr, int rank, const cuuint64_t* dims, const cuuint64_t* strides,
            const cuuint32_t* box) {
    const cuuint32_t ones[3] = {1, 1, 1};
    fn(m, CU_TENSOR_MAP_DATA_TYPE_BFLOAT16, rank, const_cast<void*>(ptr), dims, strides, box, ones,
       CU_TENSOR_MAP_INTERLEAVE_NONE, CU_TENSOR_MAP_SWIZZLE_128B, CU_TENSOR_MAP_L2_PROMOTION_L2_128B,
       CU_TENSOR_MAP_FLOAT_OOB_FILL_NONE);
}

}

extern "C" void kernel_launch(void* const* d_in, const int* in_sizes, int n_in, void* d_out, int out_size) {
    (void)in_sizes; (void)n_in; (void)out_size;
    static EncodeFn fn = nullptr;
    static void *hbuf = nullptr, *epoch = nullptr;
    static int sms = 0;
    if (!hbuf) {
        void* p = nullptr;
        cudaDriverEntryPointQueryResult q;
        cudaGetDriverEntryPoint("cuTensorMapEncodeTiled", &p, cudaEnableDefault, &q);
        fn = (EncodeFn)p;
        cudaGetSymbolAddress(&hbuf, g_h);
        cudaGetSymbolAddress(&epoch, g_epoch);
        cudaFuncSetAttribute(mlp_kernel, cudaFuncAttributeMaxDynamicSharedMemorySize, SMEM_BYTES);
        int dev = 0;
        cudaGetDevice(&dev);
        cudaDeviceGetAttribute(&sms, cudaDevAttrMultiProcessorCount, dev);
    }
    if (sms < NCTA || !fn) {
        typedef const __nv_bfloat16* P;
        fallback_h<<<dim3(D_FF / 128, S_TOK), 128, 0, cudaStreamPerThread>>>((P)d_in[0], (P)d_in[1], (P)d_in[2], (__nv_bfloat16*)hbuf);
        fallback_out<<<dim3(D_MODEL / 128, S_TOK), 128, 0, cudaStreamPerThread>>>((P)hbuf, (P)d_in[3], (P)d_in[4], (__nv_bfloat16*)d_out);
        return;
    }
    CUtensorMap mx, mw1, mw2, mo;
    {
        const cuuint64_t dims[2] = {D_MODEL, S_TOK}, str[1] = {D_MODEL * 2};
        const cuuint32_t box[2] = {64, TOK};
        encode(fn, &mx, d_in[0], 2, dims, str, box);
        encode(fn, &mo, d_out, 2, dims, str, box);
    }
    {
        const cuuint64_t dims[2] = {D_FF, D_MODEL}, str[1] = {D_FF * 2};
        const cuuint32_t box[2] = {64, 64};
        encode(fn, &mw1, d_in[1], 2, dims, str, box);
    }
    {
        const cuuint64_t dims[3] = {64, D_FF, D_MODEL / 64}, str[2] = {D_MODEL * 2, 128};
        const cuuint32_t box[3] = {64, 64, 2};
        encode(fn, &mw2, d_in[3], 3, dims, str, box);
    }
    mlp_kernel<<<NCTA, NTHREADS, SMEM_BYTES, cudaStreamPerThread>>>(
        mx, mw1, mw2, mo, (const uint8_t*)d_in[0], (const uint8_t*)d_in[1], (const uint8_t*)d_in[3],
        (const uint16_t*)d_in[2], (const uint16_t*)d_in[4], (uint8_t*)hbuf, (uint32_t*)epoch);
}
```

```cpp
#include <cuda_runtime.h>
#include <cuda_bf16.h>
#include <cuda.h>
#include <stdint.h>

namespace {

constexpr int S_TOK = 2048, D_MODEL = 640, D_FF = 1536;
constexpr int TOK = 80;
constexpr int NTILE = 26;
constexpr int NCTA = NTILE * 5;
constexpr int NTHREADS = 672;

constexpr uint32_t ASLOT = 16384, NA = 7;
constexpr uint32_t BSLOT = TOK * 128, NB = 11;
constexpr uint32_t OFF_A = 0;
constexpr uint32_t OFF_B = NA * ASLOT;
constexpr uint32_t OFF_BAR = OFF_B + NB * BSLOT;
constexpr uint32_t OFF_EPOCH = OFF_BAR + 1536;
constexpr uint32_t SMEM_BYTES = OFF_BAR + 4096;

constexpr uint32_t B_FULL1 = 0;
constexpr uint32_t B_EPOCH = 30;
constexpr uint32_t B_RAW = 32;
constexpr uint32_t B_FULL2 = 56;
constexpr uint32_t B_DONE2 = 80;
constexpr uint32_t B_DONE1 = 104;
constexpr uint32_t B_LEAD = 129;
constexpr uint32_t B_HALF = 130;
constexpr uint32_t B_END = 136;

constexpr uint32_t DESC_HI_SW128 = 0x40000040u;
constexpr uint32_t DESC_HI_H = 128 >> 4;
constexpr uint32_t H_LBO = 1280;
constexpr uint32_t SPIN_LIMIT = 1u << 21;

constexpr int NSPLIT = 3;
constexpr int HLOOK = 8;
constexpr int PF_W2 = 10, PF_N = 8;
constexpr int END_LEAD = 2;
constexpr uint32_t STORE_TICKS = 0x150f0c08;

__device__ __align__(1024) uint8_t g_h[NTILE * 24 * BSLOT];
__device__ uint32_t g_epoch[NCTA];

__device__ __forceinline__ void mbar_init(uint32_t bar, uint32_t cnt) {
    asm volatile("mbarrier.init.shared::cta.b64 [%0], %1;" ::"r"(bar), "r"(cnt) : "memory");
}
__device__ __forceinline__ void mbar_expect_tx(uint32_t bar, uint32_t bytes) {
    asm volatile("mbarrier.arrive.expect_tx.shared::cta.b64 _, [%0], %1;" ::"r"(bar), "r"(bytes) : "memory");
}
__device__ __forceinline__ void mbar_arrive(uint32_t bar) {
    asm volatile("mbarrier.arrive.shared::cta.b64 _, [%0];" ::"r"(bar) : "memory");
}
__device__ __forceinline__ void mbar_arrive_if(uint32_t bar, uint32_t pred) {
    asm volatile("{\n.reg .pred p;\nsetp.ne.u32 p, %1, 0;\n@p mbarrier.arrive.shared::cta.b64 _, [%0];\n}"
                 ::"r"(bar), "r"(pred) : "memory");
}
__device__ __forceinline__ void mbar_spin(uint32_t bar, uint32_t parity = 0) {
    asm volatile("{\n.reg .pred p;\nWAIT:\nmbarrier.try_wait.parity.shared::cta.b64 p, [%0], %1;\n@!p bra WAIT;\n}"
                 ::"r"(bar), "r"(parity) : "memory");
}
__device__ __forceinline__ void watchdog(uint32_t bar) {
    uint32_t n = 0, ok;
    do {
        asm volatile("{\n.reg .pred p;\nmbarrier.try_wait.parity.shared::cta.b64 p, [%1], 0, 1000;\nselp.u32 %0, 1, 0, p;\n}"
                     : "=r"(ok) : "r"(bar) : "memory");
        if (++n > SPIN_LIMIT) __trap();
    } while (!ok);
}
__device__ __forceinline__ bool elect_one() {
    uint32_t p;
    asm volatile("{\n.reg .pred P;\nelect.sync _|P, 0xffffffff;\nselp.u32 %0, 1, 0, P;\n}" : "=r"(p));
    return p;
}
__device__ __forceinline__ void tma_2d(uint32_t dst, const CUtensorMap* m, int c0, int c1, uint32_t bar) {
    asm volatile("cp.async.bulk.tensor.2d.shared::cluster.global.mbarrier::complete_tx::bytes [%0], [%1, {%3, %4}], [%2];"
                 ::"r"(dst), "l"(m), "r"(bar), "r"(c0), "r"(c1) : "memory");
}
__device__ __forceinline__ void tma_3d(uint32_t dst, const CUtensorMap* m, int c0, int c1, int c2, uint32_t bar) {
    asm volatile("cp.async.bulk.tensor.3d.shared::cluster.global.mbarrier::complete_tx::bytes [%0], [%1, {%3, %4, %5}], [%2];"
                 ::"r"(dst), "l"(m), "r"(bar), "r"(c0), "r"(c1), "r"(c2) : "memory");
}
__device__ __forceinline__ void tma_store_2d(const CUtensorMap* m, uint32_t src, int c0, int c1) {
    asm volatile("cp.async.bulk.tensor.2d.global.shared::cta.bulk_group [%0, {%2, %3}], [%1];"
                 ::"l"(m), "r"(src), "r"(c0), "r"(c1) : "memory");
}
__device__ __forceinline__ void bulk_load(uint32_t dst, const void* src, uint32_t bytes, uint32_t bar) {
    asm volatile("cp.async.bulk.shared::cluster.global.mbarrier::complete_tx::bytes [%0], [%1], %2, [%3];"
                 ::"r"(dst), "l"(src), "r"(bytes), "r"(bar) : "memory");
}
__device__ __forceinline__ void bulk_prefetch(const void* src, uint32_t bytes) {
    asm volatile("cp.async.bulk.prefetch.L2.global [%0], %1;" ::"l"(src), "r"(bytes) : "memory");
}
__device__ __forceinline__ void prefetch_l2(const void* p) {
    asm volatile("prefetch.global.L2 [%0];" ::"l"(p) : "memory");
}
__device__ __forceinline__ void prefetch_map(const CUtensorMap* m) {
    asm volatile("prefetch.tensormap [%0];" ::"l"(m) : "memory");
}
__device__ __forceinline__ uint32_t ldg_u16(const uint16_t* p) {
    uint32_t v;
    asm volatile("ld.global.nc.u16 %0, [%1];" : "=r"(v) : "l"(p));
    return v;
}
__device__ __forceinline__ uint32_t late(uint32_t v) {
    asm volatile("" : "+r"(v)::"memory");
    return v;
}
__device__ __forceinline__ void wg_fence() { asm volatile("wgmma.fence.sync.aligned;" ::: "memory"); }
__device__ __forceinline__ void wg_commit() { asm volatile("wgmma.commit_group.sync.aligned;" ::: "memory"); }
template <int N> __device__ __forceinline__ void wg_wait() {
    asm volatile("wgmma.wait_group.sync.aligned %0;" ::"n"(N) : "memory");
}
__device__ __forceinline__ void reg_fence(float (&d)[40]) {
#pragma unroll
    for (int i = 0; i < 40; i++) asm volatile("" : "+f"(d[i])::"memory");
}
__device__ __forceinline__ void stsm_x4_t(uint32_t addr, uint32_t a, uint32_t b, uint32_t c, uint32_t d) {
    asm volatile("stmatrix.sync.aligned.m8n8.x4.trans.shared.b16 [%0], {%1, %2, %3, %4};"
                 ::"r"(addr), "r"(a), "r"(b), "r"(c), "r"(d) : "memory");
}
__device__ __forceinline__ uint32_t pack_bf16(float lo, float hi) {
    uint32_t r;
    asm("cvt.rn.bf16x2.f32 %0, %1, %2;" : "=r"(r) : "f"(hi), "f"(lo));
    return r;
}
__device__ __forceinline__ uint32_t add_bf16(uint32_t a, uint32_t b) {
    uint32_t r;
    asm("add.rn.bf16x2 %0, %1, %2;" : "=r"(r) : "r"(a), "r"(b));
    return r;
}
__device__ __forceinline__ uint32_t act(float lo, float hi, uint32_t bias) {
    uint32_t h = add_bf16(pack_bf16(lo, hi), bias), r;
    asm("max.bf16x2 %0, %1, %2;" : "=r"(r) : "r"(h), "r"(0u));
    asm("mul.rn.bf16x2 %0, %1, %1;" : "=r"(h) : "r"(r));
    return h;
}

__device__ __forceinline__ void mma_x(float (&d)[40], uint32_t alo, uint32_t blo, uint32_t acc) {
    asm volatile(
        "{\n.reg .pred p;\n.reg .b64 da, db;\n"
        "setp.ne.b32 p, %42, 0;\n"
        "mov.b64 da, {%40, %43};\nmov.b64 db, {%41, %44};\n"
        "wgmma.mma_async.sync.aligned.m64n80k16.f32.bf16.bf16 "
        "{%0, %1, %2, %3, %4, %5, %6, %7, %8, %9, %10, %11, %12, %13, %14, %15, "
        "%16, %17, %18, %19, %20, %21, %22, %23, %24, %25, %26, %27, %28, %29, %30, %31, "
        "%32, %33, %34, %35, %36, %37, %38, %39}, "
        "da, db, p, 1, 1, 1, 0;\n}\n"
        : "+f"(d[0]), "+f"(d[1]), "+f"(d[2]), "+f"(d[3]), "+f"(d[4]), "+f"(d[5]), "+f"(d[6]), "+f"(d[7]),
          "+f"(d[8]), "+f"(d[9]), "+f"(d[10]), "+f"(d[11]), "+f"(d[12]), "+f"(d[13]), "+f"(d[14]), "+f"(d[15]),
          "+f"(d[16]), "+f"(d[17]), "+f"(d[18]), "+f"(d[19]), "+f"(d[20]), "+f"(d[21]), "+f"(d[22]), "+f"(d[23]),
          "+f"(d[24]), "+f"(d[25]), "+f"(d[26]), "+f"(d[27]), "+f"(d[28]), "+f"(d[29]), "+f"(d[30]), "+f"(d[31]),
          "+f"(d[32]), "+f"(d[33]), "+f"(d[34]), "+f"(d[35]), "+f"(d[36]), "+f"(d[37]), "+f"(d[38]), "+f"(d[39])
        : "r"(alo), "r"(blo), "r"(acc), "n"(DESC_HI_SW128), "n"(DESC_HI_SW128));
}

__device__ __forceinline__ void mma_h(float (&d)[40], uint32_t alo, uint32_t blo, uint32_t acc) {
    asm volatile(
        "{\n.reg .pred p;\n.reg .b64 da, db;\n"
        "setp.ne.b32 p, %42, 0;\n"
        "mov.b64 da, {%40, %43};\nmov.b64 db, {%41, %44};\n"
        "wgmma.mma_async.sync.aligned.m64n80k16.f32.bf16.bf16 "
        "{%0, %1, %2, %3, %4, %5, %6, %7, %8, %9, %10, %11, %12, %13, %14, %15, "
        "%16, %17, %18, %19, %20, %21, %22, %23, %24, %25, %26, %27, %28, %29, %30, %31, "
        "%32, %33, %34, %35, %36, %37, %38, %39}, "
        "da, db, p, 1, 1, 1, 1;\n}\n"
        : "+f"(d[0]), "+f"(d[1]), "+f"(d[2]), "+f"(d[3]), "+f"(d[4]), "+f"(d[5]), "+f"(d[6]), "+f"(d[7]),
          "+f"(d[8]), "+f"(d[9]), "+f"(d[10]), "+f"(d[11]), "+f"(d[12]), "+f"(d[13]), "+f"(d[14]), "+f"(d[15]),
          "+f"(d[16]), "+f"(d[17]), "+f"(d[18]), "+f"(d[19]), "+f"(d[20]), "+f"(d[21]), "+f"(d[22]), "+f"(d[23]),
          "+f"(d[24]), "+f"(d[25]), "+f"(d[26]), "+f"(d[27]), "+f"(d[28]), "+f"(d[29]), "+f"(d[30]), "+f"(d[31]),
          "+f"(d[32]), "+f"(d[33]), "+f"(d[34]), "+f"(d[35]), "+f"(d[36]), "+f"(d[37]), "+f"(d[38]), "+f"(d[39])
        : "r"(alo), "r"(blo), "r"(acc), "n"(DESC_HI_SW128), "n"(DESC_HI_H));
}

__device__ __forceinline__ void mma_hn(float (&d)[40], uint32_t alo, uint32_t blo, uint32_t acc) {
    asm volatile(
        "{\n.reg .pred p;\n.reg .b64 da, db;\n"
        "setp.ne.b32 p, %42, 0;\n"
        "mov.b64 da, {%40, %43};\nmov.b64 db, {%41, %44};\n"
        "wgmma.mma_async.sync.aligned.m64n80k16.f32.bf16.bf16 "
        "{%0, %1, %2, %3, %4, %5, %6, %7, %8, %9, %10, %11, %12, %13, %14, %15, "
        "%16, %17, %18, %19, %20, %21, %22, %23, %24, %25, %26, %27, %28, %29, %30, %31, "
        "%32, %33, %34, %35, %36, %37, %38, %39}, "
        "da, db, p, 1, -1, 1, 1;\n}\n"
        : "+f"(d[0]), "+f"(d[1]), "+f"(d[2]), "+f"(d[3]), "+f"(d[4]), "+f"(d[5]), "+f"(d[6]), "+f"(d[7]),
          "+f"(d[8]), "+f"(d[9]), "+f"(d[10]), "+f"(d[11]), "+f"(d[12]), "+f"(d[13]), "+f"(d[14]), "+f"(d[15]),
          "+f"(d[16]), "+f"(d[17]), "+f"(d[18]), "+f"(d[19]), "+f"(d[20]), "+f"(d[21]), "+f"(d[22]), "+f"(d[23]),
          "+f"(d[24]), "+f"(d[25]), "+f"(d[26]), "+f"(d[27]), "+f"(d[28]), "+f"(d[29]), "+f"(d[30]), "+f"(d[31]),
          "+f"(d[32]), "+f"(d[33]), "+f"(d[34]), "+f"(d[35]), "+f"(d[36]), "+f"(d[37]), "+f"(d[38]), "+f"(d[39])
        : "r"(alo), "r"(blo), "r"(acc), "n"(DESC_HI_SW128), "n"(DESC_HI_H));
}


__global__ void __launch_bounds__(NTHREADS, 1)
mlp_kernel(const __grid_constant__ CUtensorMap map_x, const __grid_constant__ CUtensorMap map_w1,
           const __grid_constant__ CUtensorMap map_w2, const __grid_constant__ CUtensorMap map_out,
           const uint8_t* __restrict__ x, const uint8_t* __restrict__ w1, const uint8_t* __restrict__ w2,
           const uint16_t* __restrict__ b1, const uint16_t* __restrict__ b2, uint8_t* hbuf, uint32_t* epoch,
           uint8_t* out)
{
    extern __shared__ __align__(1024) uint8_t smem_raw[];
    uint32_t sbase = (uint32_t)__cvta_generic_to_shared(smem_raw);
    asm volatile("" : "+r"(sbase));
    const int lane = threadIdx.x & 31;
    const int b = blockIdx.x;
    const int tt = b / 5, dt = b - tt * 5;
    auto bar = [&](uint32_t i) { return sbase + OFF_BAR + 8 * i; };
    auto load_x = [&](uint32_t s) {
        tma_2d(sbase + OFF_B + s * BSLOT, &map_x, s * 64, tt * TOK, bar(B_FULL1 + s));
        tma_2d(sbase + OFF_B + (s + 1) * BSLOT, &map_x, s * 64 + 64, tt * TOK, bar(B_FULL1 + s));
    };
    auto load_w1 = [&](uint32_t dst, int chunk, int k0, uint32_t fb) {
        tma_2d(dst, &map_w1, (dt + 5 * chunk) * 64, k0, fb);
        tma_2d(dst + 8192, &map_w1, (dt + 5 * chunk) * 64, k0 + 64, fb);
    };

    if (threadIdx.x - 32u < 64u) {
        const uint32_t t = threadIdx.x - 32, n = (t - 32) * NCTA + b;
        if (t < 32) prefetch_l2(x + (size_t)min(tt * TOK + dt * 16 + (int)(t & 15), S_TOK - 1) * (D_MODEL * 2) + (t >> 4) * 128);
        else if (t < 42) prefetch_l2(w1 + (size_t)(n / 10) * (D_FF * 2) + (n % 10) * 128);
    }
    if (threadIdx.x < 32) {
        auto load_half = [&](uint32_t s, uint32_t hf) {
            const uint32_t hb = bar(hf ? B_FULL1 + s : B_HALF + s), kb = (s & 6) + hf;
            mbar_expect_tx(hb, (s & 1) ? 8192 : BSLOT + 8192);
            if ((s & 1) == 0) tma_2d(sbase + OFF_B + kb * BSLOT, &map_x, kb * 64, tt * TOK, hb);
            tma_2d(sbase + OFF_A + s * ASLOT + hf * 8192, &map_w1, (dt + 5 * (s & 1)) * 64, kb * 64, hb);
        };
        if (elect_one()) {
#pragma unroll
            for (int s = 0; s < 2 * NSPLIT; s++) mbar_init(bar(B_HALF + s), 1);
#pragma unroll
            for (int s = 0; s < 7; s++) mbar_init(bar(B_FULL1 + s), 1);
            load_half(0, 0);
        }
        __syncwarp();
        asm volatile("bar.arrive 3, 288;" ::: "memory");
        asm volatile("bar.arrive 4, 384;" ::: "memory");
        if (elect_one()) {
#pragma unroll
            for (uint32_t i = 0; i < NSPLIT; i++) {
                if (i) load_half(2 * i, 0);
                load_half(2 * i + 1, 0);
                load_half(2 * i, 1);
                load_half(2 * i + 1, 1);
            }
#pragma unroll
            for (uint32_t s = 2 * NSPLIT; s < 7; s++) {
                mbar_expect_tx(bar(B_FULL1 + s), (s & 1) ? ASLOT : ASLOT + 2 * BSLOT);
                if ((s & 1) == 0) load_x(s);
                load_w1(sbase + OFF_A + s * ASLOT, s & 1, (s >> 1) * 128, bar(B_FULL1 + s));
            }
        }
        __syncwarp();
    }

    const int hw = __shfl_sync(0xffffffffu, threadIdx.x >> 5, 0);
    const int warp = hw < 4 ? hw + 8 : hw < 8 ? hw : hw < 12 ? hw - 8 : hw;
    const int nchunk = dt < 4 ? 5 : 4;
    const int n1 = nchunk * 5;
    auto parity = [&]() {
        uint32_t v;
        mbar_spin(bar(B_EPOCH));
        asm volatile("ld.shared.u32 %0, [%1];" : "=r"(v) : "r"(sbase + OFF_EPOCH) : "memory");
        return v & 1;
    };

    uint32_t early[6];
    if (warp < 8) {
        asm volatile("bar.sync 3, 288;" ::: "memory");
    } else if (warp == 20) {
        if (elect_one()) mbar_init(bar(B_END), 8);
        __syncwarp();
        asm volatile("bar.arrive 6, 640;" ::: "memory");
        watchdog(bar(B_END));
        return;
    } else {
        if (warp == 17) early[0] = epoch[b];
        if (warp > 8 && elect_one()) {
            const uint32_t w = warp - 9;
            const uint32_t first = w < 2 ? 7 + w * 12 : w < 8 ? B_RAW + (w - 2) * 12 : B_DONE1 + (w - 8) * 7;
            const uint32_t cnt = w < 4 ? 1 : w < 6 ? 2 : w < 8 ? 8 : 4;
#pragma unroll
            for (uint32_t i = 0; i < 7; i++) mbar_init(bar(first + i), cnt);
            if (w < 8 || w == 10) {
#pragma unroll
                for (uint32_t i = 7; i < 12; i++) mbar_init(bar(first + i), cnt);
            }
        }
        __syncwarp();
        if (warp == 8) {
            asm volatile("bar.sync 5, 64;" ::: "memory");
        } else {
            asm volatile("bar.arrive 6, 640;" ::: "memory");
            asm volatile("bar.sync 4, 384;" ::: "memory");
        }
        if (warp == 9) asm volatile("bar.arrive 5, 64;" ::: "memory");
    }

    if (warp < 16) {
        const int wg = warp >> 2;
        {
            const int r = (warp & 3) * 16 + (lane >> 2);
#pragma unroll
            for (int i = 0; i < 2; i++) {
                const int g = min(dt + 5 * (wg == 3 ? 4 : wg + 3 * i), 23);
                early[2 * i] = ldg_u16(b1 + g * 64 + r);
                early[2 * i + 1] = ldg_u16(b1 + g * 64 + r + 8);
            }
            early[4] = ldg_u16(b2 + dt * 128 + (wg >> 1) * 64 + r);
            early[5] = ldg_u16(b2 + dt * 128 + (wg >> 1) * 64 + r + 8);
        }
        const uint32_t lo = (sbase & 0x3FFFFu) >> 4;
        const uint32_t dA = lo + (OFF_A >> 4) + (1u << 16);
        const uint32_t dX = lo + (OFF_B >> 4) + (1u << 16);
        const uint32_t dH = lo + (OFF_B >> 4) + ((H_LBO >> 4) << 16);
        const uint32_t lead = lane == 0;
        float acc[40];
        auto half = [&](uint32_t a, uint32_t xb, bool first) {
#pragma unroll
            for (int kk = 0; kk < 4; kk++) mma_x(acc, a + kk * 128, xb + kk * 2, !(first && kk == 0));
        };
        auto store_h = [&](int c, uint32_t blo, uint32_t bhi) {
            reg_fence(acc);
            const uint32_t tag = parity() * 0x80008000u;
            uint32_t pk[20];
            blo = late(blo) * 0x10001u;
            bhi = late(bhi) * 0x10001u;
#pragma unroll
            for (int g = 0; g < 10; g++) {
                pk[2 * g] = act(acc[4 * g], acc[4 * g + 1], blo) | tag;
                pk[2 * g + 1] = act(acc[4 * g + 2], acc[4 * g + 3], bhi) | tag;
            }
            const int t0 = c == 4 ? 26 : (STORE_TICKS >> (8 * c)) & 255;
            auto tick = [&](int t) { mbar_spin(bar(t < n1 ? B_DONE1 + t : B_DONE2 + t - n1)); };
            uint8_t* dst = hbuf + (size_t)(tt * 24 + dt + 5 * c) * BSLOT + (warp & 3) * 2560 + lane * 4;
#pragma unroll
            for (int g = 0; g < 10; g++) {
                if (c == 4) tick(t0 + g);
                else if (c == 3) { if (g % 2 == 0) tick(t0 + g / 2); }
                else if (g == 0 || g == 4 || g == 7) tick(t0 + g / 3);
                asm volatile("st.global.u32 [%0], %1;" ::"l"(dst + g * 128), "r"(pk[2 * g]) : "memory");
                asm volatile("st.global.u32 [%0], %1;" ::"l"(dst + 1280 + g * 128), "r"(pk[2 * g + 1]) : "memory");
            }
        };

        if (wg < 2) {
            const uint32_t fb = bar(B_FULL1 + wg), db = bar(B_DONE1 + wg);
#pragma unroll
            for (int i = 0; i < 5; i++) {
                const uint32_t a = dA + (wg ? (2 * i + 1) % NA : (2 * i) % NA) * (ASLOT >> 4);
                if (i < NSPLIT) {
                    mbar_spin(bar(B_HALF + 2 * i));
                    mbar_spin(bar(B_HALF + 2 * i + wg));
                    wg_fence();
                    half(a, dX + 2 * i * (BSLOT >> 4), i == 0);
                    wg_commit();
                    if (i == 0) asm volatile("bar.sync 6, 640;" ::: "memory");
                    mbar_spin(bar(B_FULL1 + 2 * i));
                    mbar_spin(fb + 16 * i);
                    wg_fence();
                    half(a + 512, dX + (2 * i + 1) * (BSLOT >> 4), false);
                    wg_commit();
                    if (i > 0) wg_wait<2>();
                } else {
                    mbar_spin(bar(B_FULL1 + 2 * i));
                    mbar_spin(fb + 16 * i);
                    wg_fence();
                    half(a, dX + 2 * i * (BSLOT >> 4), false);
                    half(a + 512, dX + (2 * i + 1) * (BSLOT >> 4), false);
                    wg_commit();
                    wg_wait<1>();
                }
                if (i > 0) mbar_arrive_if(db + 16 * (i - 1), lead);
            }
            wg_wait<0>();
            mbar_arrive_if(db + 64, lead);
            store_h(wg, early[0], early[1]);
        }
        const int c = wg == 0 ? 3 : wg == 1 ? 5 : 2 * wg - 2;
        if (c < nchunk) {
            const uint32_t fb = bar(B_FULL1 + 5 * c), db = bar(B_DONE1 + 5 * c);
            uint32_t slot = c == 2 ? 10 % NA : c == 3 ? 15 % NA : 20 % NA;
            if (c == 2) mbar_spin(bar(B_FULL1 + 8));
            mbar_spin(fb);
            mbar_spin(db - (c == 2 ? 24 : 16));
#pragma unroll
            for (int i = 0; i < 5; i++) {
                const uint32_t a = dA + slot * (ASLOT >> 4);
                slot = slot == NA - 1 ? 0 : slot + 1;
                wg_fence();
                half(a, dX + 2 * i * (BSLOT >> 4), i == 0);
                half(a + 512, dX + (2 * i + 1) * (BSLOT >> 4), false);
                wg_commit();
                if (i < 4) mbar_spin(fb + 8 * (i + 1));
                if (i > 0) {
                    wg_wait<1>();
                    mbar_arrive_if(db + 8 * (i - 1), lead);
                }
            }
            wg_wait<0>();
            mbar_arrive_if(db + 32, lead);
            store_h(c, wg ? early[0] : early[2], wg ? early[1] : early[3]);
        }
        if (wg == 0 || wg == 3) return;

        const int dh = wg >> 1;
        uint32_t a2 = dA + (dt < 4 ? 25 % NA : 20 % NA) * (ASLOT >> 4) + dh * 512, h2 = dH + 10 * (BSLOT >> 4);
        const uint32_t a2_last = dA + (NA - 1) * (ASLOT >> 4) + dh * 512, h2_last = h2;
        uint32_t fb2 = bar(B_FULL2);
        const int hold_at = dh ? 24 - END_LEAD : -1;
#define STEP2(MMA, p)                                                                               \
        {                                                                                           \
            wg_fence();                                                                             \
            _Pragma("unroll") for (int kk = 0; kk < 4; kk++)                                        \
                MMA(acc, a2 + kk * 128, h2 + kk * (2 * H_LBO >> 4), ((p) | kk) != 0);               \
            wg_commit();                                                                            \
            a2 = a2 == a2_last ? a2 - (NA - 1) * (ASLOT >> 4) : a2 + (ASLOT >> 4);                  \
            h2 = h2 == h2_last ? dH : h2 + (BSLOT >> 4);                                            \
            fb2 += 8;                                                                               \
        }
#define PHASE2(MMA)                                                                                 \
        STEP2(MMA, 0);                                                                              \
        mbar_spin(fb2);                                                                             \
        _Pragma("unroll 1") for (int p = 1; p < 23; p++) {                                          \
            if (p == hold_at) mbar_spin(bar(B_LEAD));                                               \
            STEP2(MMA, p);                                                                          \
            mbar_spin(fb2);                                                                         \
            wg_wait<1>();                                                                           \
            mbar_arrive_if(fb2 + 8 * (B_DONE2 - B_FULL2 - 2), lead);                                \
        }                                                                                           \
        STEP2(MMA, 23);                                                                             \
        mbar_arrive_if(bar(B_LEAD), lead && !dh);                                                   \
        wg_wait<0>();
        const uint32_t odd = __shfl_sync(0xffffffffu, parity(), 0);
        mbar_spin(fb2);
        mbar_spin(bar(B_DONE1 + n1 - 2));
        if (odd) { PHASE2(mma_hn) } else { PHASE2(mma_h) }
#undef PHASE2
#undef STEP2
        const uint32_t b2lo = late(early[4]) * 0x10001u, b2hi = late(early[5]) * 0x10001u;
        reg_fence(acc);
        mbar_arrive_if(bar(B_END), lead);

        const uint32_t otile = sbase + OFF_B + (2 + dh) * BSLOT;
        const uint32_t orow = otile + ((lane >> 4) * 8 + (lane & 7)) * 128 +
                              ((uint32_t)((((warp & 3) * 2 + ((lane >> 3) & 1)) ^ (lane & 7))) << 4);
#pragma unroll
        for (int g = 0; g < 10; g += 2) {
            const int i = g * 4;
            const uint32_t m0 = add_bf16(pack_bf16(acc[i + 0], acc[i + 1]), b2lo);
            const uint32_t m1 = add_bf16(pack_bf16(acc[i + 2], acc[i + 3]), b2hi);
            const uint32_t m2 = add_bf16(pack_bf16(acc[i + 4], acc[i + 5]), b2lo);
            const uint32_t m3 = add_bf16(pack_bf16(acc[i + 6], acc[i + 7]), b2hi);
            stsm_x4_t(orow + g * 1024, m0, m1, m2, m3);
        }
        if (dh) {
            asm volatile("bar.sync 2, 128;" ::: "memory");
            const int r0 = (warp & 3) * 4 + (lane >> 3);
            const uint32_t src = otile + r0 * 128 + (((lane & 7) ^ (r0 & 7)) << 4);
            uint8_t* dst = out + (size_t)(tt * TOK + r0) * (D_MODEL * 2) + dt * 256 + 128 + (lane & 7) * 16;
            uint4 v[5];
#pragma unroll
            for (int i = 0; i < 5; i++)
                asm volatile("ld.shared.v4.u32 {%0, %1, %2, %3}, [%4];"
                             : "=r"(v[i].x), "=r"(v[i].y), "=r"(v[i].z), "=r"(v[i].w) : "r"(src + i * 2048) : "memory");
#pragma unroll
            for (int i = 0; i < 5; i++)
                if (tt * TOK + r0 + i * 16 < S_TOK)
                    asm volatile("st.global.v4.u32 [%0], {%1, %2, %3, %4};"
                                 ::"l"(dst + i * 16 * (D_MODEL * 2)), "r"(v[i].x), "r"(v[i].y), "r"(v[i].z), "r"(v[i].w) : "memory");
        } else {
            asm volatile("bar.sync 1, 128;" ::: "memory");
            if ((warp & 3) == 0 && elect_one()) {
                asm volatile("fence.proxy.async.shared::cta;" ::: "memory");
                tma_store_2d(&map_out, otile, dt * 128, tt * TOK);
                asm volatile("cp.async.bulk.commit_group;" ::: "memory");
                asm volatile("cp.async.bulk.wait_group.read 0;" ::: "memory");
            }
        }
    } else if (warp == 16) {
        if (elect_one()) {
            prefetch_map(&map_w2);
            prefetch_map(&map_out);
            uint32_t dst = sbase + OFF_A, fb = bar(B_FULL1 + NA), db = bar(B_DONE1);
            auto next = [&]() {
                dst = dst == sbase + OFF_A + (NA - 1) * ASLOT ? sbase + OFF_A : dst + ASLOT;
                fb += 8;
                db += 8;
            };
            mbar_spin(bar(B_HALF));
            load_x(8);
#pragma unroll 1
            for (int s = NA; s < n1; s++) {
                const int chunk = s < 10 ? (s & 1) : s / 5, k0 = (s < 10 ? s >> 1 : s % 5) * 128;
                mbar_spin(db);
                load_w1(dst, chunk, k0, fb);
                next();
            }
            const uint8_t* hsrc = hbuf + (size_t)tt * 24 * BSLOT;
            auto load_h = [&](int p) {
                bulk_load(sbase + OFF_B + ((p + 10) % NB) * BSLOT, hsrc + p * BSLOT, BSLOT, bar(B_RAW + p));
            };
            fb = bar(B_FULL2);
#pragma unroll
            for (int q = 0; q < 25; q++) {
                if (q == NA) db = bar(B_DONE2);
                mbar_spin(db);
#pragma unroll
                for (int p = 0; p < 24; p++) {
                    const int due = p == 0 ? 0 : p < HLOOK ? 2 + max(p + 5 - HLOOK, (p - 1) >> 1) : p - HLOOK + 7;
                    if (p < 20) { if (due == q) load_h(p); }
                    else if (due == q) { if (dt < 4) load_h(p); }
                    else if (q == min(due + 5, 24) && dt == 4) load_h(p);
                }
                if (q < 24) tma_3d(dst, &map_w2, 0, q * 64, 2 * dt, fb);
                next();
            }
        }
    } else if (warp == 17) {
        if (elect_one()) {
#pragma unroll 1
            for (int s = NA; s < 25; s++) mbar_expect_tx(bar(B_FULL1 + s), s == 8 ? ASLOT + 2 * BSLOT : ASLOT);
            const uint32_t now = early[0] + 1;
            asm volatile("st.shared.u32 [%0], %1;" ::"r"(sbase + OFF_EPOCH), "r"(now) : "memory");
            mbar_arrive(bar(B_EPOCH));
            epoch[b] = now;
#pragma unroll 1
            for (int p = 0; p < 24; p++) {
                mbar_expect_tx(bar(B_FULL2 + p), ASLOT);
                mbar_expect_tx(bar(B_RAW + p), BSLOT);
            }
            if (b < 128) {
#pragma unroll 1
                for (int i = 0; i < PF_N; i++) {
                    mbar_spin(bar(B_FULL1 + PF_W2 + i));
                    bulk_prefetch(w2 + (size_t)i * (D_FF * D_MODEL * 2 / PF_N) + b * (15360 / PF_N), 15360 / PF_N);
                }
            }
        }
    } else {
        const uint32_t flip = parity() ? 0u : 0x80008000u;
        const uint32_t off = lane * 32 + ((lane >> 2) & 7) * 4;
#pragma unroll 1
        for (int p = warp - 18; p < 24; p += 2) {
            const uint32_t tile = sbase + OFF_B + ((p + 10) % NB) * BSLOT, raw = bar(B_RAW + p);
            for (uint32_t tries = 0;; tries++) {
                mbar_spin(raw, tries & 1);
                uint32_t ok = 0x80008000u;
#pragma unroll
                for (int i = 0; i < 10; i++) {
                    uint32_t v;
                    asm volatile("ld.shared.u32 %0, [%1];" : "=r"(v) : "r"(tile + off + i * 1024) : "memory");
                    ok &= v ^ flip;
                }
                if (__all_sync(0xffffffffu, ok == 0x80008000u)) break;
                if (elect_one()) {
                    mbar_expect_tx(raw, BSLOT);
                    bulk_load(tile, hbuf + (size_t)(tt * 24 + p) * BSLOT, BSLOT, raw);
                }
                __syncwarp();
            }
            mbar_arrive_if(bar(B_FULL2 + p), lane == 0);
        }
    }
}

__device__ __forceinline__ float rbf(float v) { return __bfloat162float(__float2bfloat16(v)); }
__global__ void fallback_h(const __nv_bfloat16* x, const __nv_bfloat16* w1, const __nv_bfloat16* b1, __nv_bfloat16* h) {
    const int f = blockIdx.x * blockDim.x + threadIdx.x, t = blockIdx.y;
    float a = 0.f;
    for (int k = 0; k < D_MODEL; k++) a += __bfloat162float(x[t * D_MODEL + k]) * __bfloat162float(w1[k * D_FF + f]);
    float v = rbf(rbf(a) + __bfloat162float(b1[f]));
    v = v > 0.f ? v : 0.f;
    h[t * D_FF + f] = __float2bfloat16(v * v);
}
__global__ void fallback_out(const __nv_bfloat16* h, const __nv_bfloat16* w2, const __nv_bfloat16* b2, __nv_bfloat16* out) {
    const int d = blockIdx.x * blockDim.x + threadIdx.x, t = blockIdx.y;
    float a = 0.f;
    for (int k = 0; k < D_FF; k++) a += __bfloat162float(h[t * D_FF + k]) * __bfloat162float(w2[k * D_MODEL + d]);
    out[t * D_MODEL + d] = __float2bfloat16(rbf(a) + __bfloat162float(b2[d]));
}

typedef CUresult (*EncodeFn)(CUtensorMap*, CUtensorMapDataType, cuuint32_t, void*, const cuuint64_t*, const cuuint64_t*,
                             const cuuint32_t*, const cuuint32_t*, CUtensorMapInterleave, CUtensorMapSwizzle,
                             CUtensorMapL2promotion, CUtensorMapFloatOOBfill);

void encode(EncodeFn fn, CUtensorMap* m, const void* ptr, int rank, const cuuint64_t* dims, const cuuint64_t* strides,
            const cuuint32_t* box) {
    const cuuint32_t ones[3] = {1, 1, 1};
    fn(m, CU_TENSOR_MAP_DATA_TYPE_BFLOAT16, rank, const_cast<void*>(ptr), dims, strides, box, ones,
       CU_TENSOR_MAP_INTERLEAVE_NONE, CU_TENSOR_MAP_SWIZZLE_128B, CU_TENSOR_MAP_L2_PROMOTION_L2_128B,
       CU_TENSOR_MAP_FLOAT_OOB_FILL_NONE);
}

}

extern "C" void kernel_launch(void* const* d_in, const int* in_sizes, int n_in, void* d_out, int out_size) {
    (void)in_sizes; (void)n_in; (void)out_size;
    static EncodeFn fn = nullptr;
    static void *hbuf = nullptr, *epoch = nullptr;
    static int sms = 0;
    if (!hbuf) {
        void* p = nullptr;
        cudaDriverEntryPointQueryResult q;
        cudaGetDriverEntryPoint("cuTensorMapEncodeTiled", &p, cudaEnableDefault, &q);
        fn = (EncodeFn)p;
        cudaGetSymbolAddress(&hbuf, g_h);
        cudaGetSymbolAddress(&epoch, g_epoch);
        cudaFuncSetAttribute(mlp_kernel, cudaFuncAttributeMaxDynamicSharedMemorySize, SMEM_BYTES);
        int dev = 0;
        cudaGetDevice(&dev);
        cudaDeviceGetAttribute(&sms, cudaDevAttrMultiProcessorCount, dev);
    }
    if (sms < NCTA || !fn) {
        typedef const __nv_bfloat16* P;
        fallback_h<<<dim3(D_FF / 128, S_TOK), 128, 0, cudaStreamPerThread>>>((P)d_in[0], (P)d_in[1], (P)d_in[2], (__nv_bfloat16*)hbuf);
        fallback_out<<<dim3(D_MODEL / 128, S_TOK), 128, 0, cudaStreamPerThread>>>((P)hbuf, (P)d_in[3], (P)d_in[4], (__nv_bfloat16*)d_out);
        return;
    }
    CUtensorMap mx, mw1, mw2, mo;
    {
        const cuuint64_t dims[2] = {D_MODEL, S_TOK}, str[1] = {D_MODEL * 2};
        const cuuint32_t box[2] = {64, TOK};
        encode(fn, &mx, d_in[0], 2, dims, str, box);
        encode(fn, &mo, d_out, 2, dims, str, box);
    }
    {
        const cuuint64_t dims[2] = {D_FF, D_MODEL}, str[1] = {D_FF * 2};
        const cuuint32_t box[2] = {64, 64};
        encode(fn, &mw1, d_in[1], 2, dims, str, box);
    }
    {
        const cuuint64_t dims[3] = {64, D_FF, D_MODEL / 64}, str[2] = {D_MODEL * 2, 128};
        const cuuint32_t box[3] = {64, 64, 2};
        encode(fn, &mw2, d_in[3], 3, dims, str, box);
    }
    mlp_kernel<<<NCTA, NTHREADS, SMEM_BYTES, cudaStreamPerThread>>>(
        mx, mw1, mw2, mo, (const uint8_t*)d_in[0], (const uint8_t*)d_in[1], (const uint8_t*)d_in[3],
        (const uint16_t*)d_in[2], (const uint16_t*)d_in[4], (uint8_t*)hbuf, (uint32_t*)epoch, (uint8_t*)d_out);
}
```
